```python
import torch

def _softmax(x, axis=-1):
    return torch.softmax(x, dim=axis)
def _gelu(x):
    return torch.nn.functional.gelu(x, approximate="tanh")
def _silu(x):
    return torch.nn.functional.silu(x)
def _sigmoid(x):
    return torch.sigmoid(x)
def _layernorm(x, axis=-1, eps=1e-5):
    m = x.mean(dim=axis, keepdim=True)
    v = x.var(dim=axis, keepdim=True, unbiased=False)
    return (x - m) / torch.sqrt(v + eps)
def _scatter_add(tgt, idx, src, axis=0):
    return tgt.clone().index_add_(axis, idx, src)
def _segment_sum(src, seg, n):
    out = torch.zeros((n,) + src.shape[1:], dtype=src.dtype)
    return out.index_add_(0, seg, src)
def _pad(x, pw):
    flat = tuple(v for pair in reversed(pw) for v in pair)
    return torch.nn.functional.pad(x, flat)

kernel_name = 'recurrent_scan__sliding_block_cached__geglu_ffn__decode'

def setup_inputs():

    _w = (lambda a: (lambda t: t.to(torch.bfloat16) if t.is_floating_point() else t)(torch.as_tensor(a)))
    def _A_setup():
        B, Sq, D = 2, 1, 448
        Hq, Hkv, Sk, Dh = 16, 8, 32768, 256
        assert Hq % Hkv == 0, (Hq, Hkv)
        return {
            "x": _w((lambda *s: torch.randn(*s, dtype=torch.bfloat16) * 0.05)(B, Sq, D)),
            "k_cache": _w((lambda *s: torch.randn(*s, dtype=torch.bfloat16) * 1.6)(B, Hkv, Sk, Dh)),
            "v_cache": _w((lambda *s: torch.randn(*s, dtype=torch.bfloat16) * 0.2)(B, Hkv, Sk, Dh)),
            "wq": _w((lambda *s: torch.randn(*s, dtype=torch.bfloat16) * 1.6)(D, Hq * Dh) * (D ** -0.5)),
            "wo": _w((lambda *s: torch.randn(*s, dtype=torch.bfloat16) * 0.2)(Hq * Dh, D) * ((Hq * Dh) ** -0.5)),
        }
    _A_in = _A_setup()

    def _B_setup():
        B, S, D, F = 2, 1, 448, 1792
        return {
            "x": _w((lambda *s: torch.randn(*s, dtype=torch.bfloat16) * 0.05)(B, S, D)),
            "w_gate": _w((lambda *s: torch.randn(*s, dtype=torch.bfloat16) * 0.1)(D, F)),
            "w_up": _w((lambda *s: torch.randn(*s, dtype=torch.bfloat16) * 0.1)(D, F)),
            "w_down": _w((lambda *s: torch.randn(*s, dtype=torch.bfloat16) * 0.1)(F, D)),
        }
    _B_in = _B_setup()

    return {
        "A_x": _A_in["x"],
        "A_k_cache": _A_in["k_cache"],
        "A_v_cache": _A_in["v_cache"],
        "A_wq": _A_in["wq"],
        "A_wo": _A_in["wo"],
        "B_x": _B_in["x"],
        "B_w_gate": _B_in["w_gate"],
        "B_w_up": _B_in["w_up"],
        "B_w_down": _B_in["w_down"],
    }

def reference(A_x, A_k_cache, A_v_cache, A_wq, A_wo, B_x, B_w_gate, B_w_up, B_w_down):
    def _A_ref(x, k_cache, v_cache, wq, wo):
        B, Sq, D = x.shape
        Hq, Dh = 16, 256
        Hkv, Sk = k_cache.shape[1], k_cache.shape[2]
        W = min(4096, max(256, Sk // 4))
        rep = Hq // Hkv
        q = (lambda x, *d: x.permute(*d))((x @ wq).reshape(B, Sq, Hq, Dh), 0, 2, 1, 3)
        k = (lambda x, n, axis: torch.repeat_interleave(x, n, dim=axis))(k_cache[:, :, Sk - W:, :], rep, axis=1)
        v = (lambda x, n, axis: torch.repeat_interleave(x, n, dim=axis))(v_cache[:, :, Sk - W:, :], rep, axis=1)
        scores = torch.einsum("bhqd,bhkd->bhqk", q, k) * (Dh ** -0.5)
        p = _softmax(scores, axis=-1)
        o = torch.einsum("bhqk,bhkd->bhqd", p, v)
        return (lambda x, *d: x.permute(*d))(o, 0, 2, 1, 3).reshape(B, Sq, Hq * Dh) @ wo

    def _B_ref(x, w_gate, w_up, w_down):
        return (_gelu(x @ w_gate) * (x @ w_up)) @ w_down

    x = A_x
    xn = _layernorm(x, axis=-1)
    s = _A_ref(xn, A_k_cache, A_v_cache, A_wq, A_wo)
    g = _silu(_B_ref(xn, B_w_gate, B_w_up, B_w_down))
    return x + s * g
```

```cpp
#include <cuda_runtime.h>
#include <cuda_bf16.h>
#include <cuda.h>
#include <stdint.h>

namespace {

constexpr int D = 448, SK = 32768, WIN = 4096, FF = 1792, QD = 4096;
constexpr int NATT = 64;
constexpr int NHELP = 28;
constexpr int MAXCTA = NATT + 7 * 8;
constexpr int CH = 64;
constexpr int CHB = CH * 512;
constexpr int WB = 224 * 128;
constexpr int NS = 6;
constexpr int NK = 16;
constexpr int I_K = 2, I_V = I_K + NK, I_WO = I_V + NK, NITEM = I_WO + 4;
constexpr int PER = 660;
constexpr int OFF = -350;
constexpr int D_WO = 750;
constexpr int MINF = 3, MAXF = 5;
constexpr int T_WD7 = 24050, T_WD4 = 24000;
constexpr int NMAIN = 320;
constexpr int NTHREADS = NMAIN + 256;
constexpr int SPIN_LIMIT = 1 << 20;

constexpr int SM_RING = 0;
constexpr int SM_XN = NS * CHB;
constexpr int SM_RED = SM_XN + 2 * 240 * 4;
constexpr int SM_QS = SM_RED + 7 * 128 * 4;
constexpr int SM_SC = SM_QS + 2 * 272 * 4;
constexpr int SM_P = SM_SC + 2 * 1024 * 4;
constexpr int SM_WMAX = SM_P + 2 * 528 * 4;
constexpr int SM_WSUM = SM_WMAX + 64;
constexpr int SM_ST = SM_WSUM + 32;
constexpr int SM_OI = SM_ST + 64;
constexpr int SM_BAR = SM_OI + 8 * 84 * 4;
constexpr int B_FULL = 0, B_CLR = NS, B_Q = NS + 1, B_ST = NS + 2, B_O = NS + 3, B_EMPTY = NS + 4, NBAR = 2 * NS + 4;
__host__ __device__ constexpr uint32_t slot_addr(int item) { return SM_RING + (item % NS) * CHB; }
__host__ __device__ constexpr uint32_t full_bar(int item) { return (B_FULL + item % NS) * 8; }
__host__ __device__ constexpr uint32_t full_par(int item) { return (item / NS) & 1; }
constexpr int SMEM_BYTES = SM_BAR + NBAR * 8 + 1024;

constexpr uint32_t EMPTY = 0xFFFFFFFFu;
__device__ __align__(128) uint32_t g_att[NHELP * 64 * 32];
__device__ __align__(128) uint32_t g_h[56 * 256];

__device__ __forceinline__ void mbar_init(uint32_t bar, uint32_t cnt) {
    asm volatile("mbarrier.init.shared::cta.b64 [%0], %1;" ::"r"(bar), "r"(cnt) : "memory");
}
__device__ __forceinline__ void mbar_expect_tx(uint32_t bar, uint32_t bytes) {
    asm volatile("mbarrier.arrive.expect_tx.shared::cta.b64 _, [%0], %1;" ::"r"(bar), "r"(bytes) : "memory");
}
__device__ __forceinline__ void mbar_arrive(uint32_t bar) {
    asm volatile("mbarrier.arrive.shared::cta.b64 _, [%0];" ::"r"(bar) : "memory");
}
__device__ __forceinline__ void mbar_wait(uint32_t bar, uint32_t parity) {
    asm volatile(
        "{\n.reg .pred p;\n.reg .u32 n;\nmov.u32 n, %2;\n"
        "W%=:\nmbarrier.try_wait.parity.shared::cta.b64 p, [%0], %1;\n@p bra.uni D%=;\n"
        "add.u32 n, n, -1;\nsetp.ne.u32 p, n, 0;\n@p bra.uni W%=;\ntrap;\nD%=:\n}"
        ::"r"(bar), "r"(parity), "n"(SPIN_LIMIT) : "memory");
}
constexpr uint64_t POLICY = 0x12F0000000000000ull;
__device__ __forceinline__ bool mbar_test(uint32_t bar, uint32_t parity) {
    uint32_t ok;
    asm volatile("{\n.reg .pred p;\nmbarrier.test_wait.parity.shared::cta.b64 p, [%1], %2;\nselp.u32 %0, 1, 0, p;\n}"
                 : "=r"(ok) : "r"(bar), "r"(parity) : "memory");
    return ok;
}
__device__ __forceinline__ uint32_t now_ns() {
    uint32_t t;
    asm volatile("mov.u32 %0, %%globaltimer_lo;" : "=r"(t));
    return t;
}
__device__ __forceinline__ void bulk_load(uint32_t dst, const void* src, uint32_t bytes, uint32_t bar) {
    asm volatile("cp.async.bulk.shared::cluster.global.mbarrier::complete_tx::bytes.L2::cache_hint [%0], [%1], %2, [%3], %4;"
                 ::"r"(dst), "l"(src), "r"(bytes), "r"(bar), "l"(POLICY) : "memory");
}
__device__ __forceinline__ void tma3d(uint32_t dst, const CUtensorMap* tm, int row, uint32_t bar) {
    asm volatile("cp.async.bulk.tensor.3d.shared::cluster.global.mbarrier::complete_tx::bytes.L2::cache_hint [%0], [%1, {%3, %4, %3}], [%2], %5;"
                 ::"r"(dst), "l"(tm), "r"(bar), "r"(0), "r"(row), "l"(POLICY) : "memory");
}
__device__ __forceinline__ void tma2d(uint32_t dst, const CUtensorMap* tm, int col, int row, uint32_t bar) {
    asm volatile("cp.async.bulk.tensor.2d.shared::cluster.global.mbarrier::complete_tx::bytes.L2::cache_hint [%0], [%1, {%3, %4}], [%2], %5;"
                 ::"r"(dst), "l"(tm), "r"(bar), "r"(col), "r"(row), "l"(POLICY) : "memory");
}
__device__ __forceinline__ uint32_t mapa(uint32_t addr, uint32_t rank) {
    uint32_t r;
    asm("mapa.shared::cluster.u32 %0, %1, %2;" : "=r"(r) : "r"(addr), "r"(rank));
    return r;
}
__device__ __forceinline__ void st_async(uint32_t addr, uint32_t v, uint32_t bar) {
    asm volatile("st.async.shared::cluster.mbarrier::complete_tx::bytes.b32 [%0], %1, [%2];" ::"r"(addr), "r"(v), "r"(bar) : "memory");
}
__device__ __forceinline__ void st_async4(uint32_t addr, float a, float b, float c, float d, uint32_t bar) {
    asm volatile("st.async.shared::cluster.mbarrier::complete_tx::bytes.v4.f32 [%0], {%1,%2,%3,%4}, [%5];"
                 ::"r"(addr), "f"(a), "f"(b), "f"(c), "f"(d), "r"(bar) : "memory");
}
__device__ __forceinline__ uint4 ld_rlx4(const uint32_t* p) {
    uint4 v;
    asm volatile("ld.relaxed.gpu.global.v4.u32 {%0,%1,%2,%3}, [%4];"
                 : "=r"(v.x), "=r"(v.y), "=r"(v.z), "=r"(v.w) : "l"(p) : "memory");
    return v;
}
__device__ __forceinline__ void st_rlx4(uint32_t* p, uint32_t v) {
    asm volatile("st.relaxed.gpu.global.v4.u32 [%0], {%1,%1,%1,%1};" ::"l"(p), "r"(v) : "memory");
}
__device__ __forceinline__ bool empty4(const uint4& v) { return max(max(v.x, v.y), max(v.z, v.w)) == EMPTY; }
__device__ __forceinline__ void ldsm4(uint32_t (&r)[4], uint32_t a) {
    asm volatile("ldmatrix.sync.aligned.m8n8.x4.shared.b16 {%0,%1,%2,%3}, [%4];"
                 : "=r"(r[0]), "=r"(r[1]), "=r"(r[2]), "=r"(r[3]) : "r"(a) : "memory");
}
__device__ __forceinline__ void ldsm4t(uint32_t (&r)[4], uint32_t a) {
    asm volatile("ldmatrix.sync.aligned.m8n8.x4.trans.shared.b16 {%0,%1,%2,%3}, [%4];"
                 : "=r"(r[0]), "=r"(r[1]), "=r"(r[2]), "=r"(r[3]) : "r"(a) : "memory");
}
__device__ __forceinline__ void mma(float (&d)[4], uint32_t a0, uint32_t a1, uint32_t a2, uint32_t a3, uint32_t b0, uint32_t b1) {
    asm volatile("mma.sync.aligned.m16n8k16.row.col.f32.bf16.bf16.f32 {%0,%1,%2,%3}, {%4,%5,%6,%7}, {%8,%9}, {%0,%1,%2,%3};"
                 : "+f"(d[0]), "+f"(d[1]), "+f"(d[2]), "+f"(d[3]) : "r"(a0), "r"(a1), "r"(a2), "r"(a3), "r"(b0), "r"(b1));
}
__device__ __forceinline__ void bar_consumers() { asm volatile("bar.sync 1, 256;" ::: "memory"); }
__device__ __forceinline__ float bf_lo(uint32_t w) { return __uint_as_float(w << 16); }
__device__ __forceinline__ float bf_hi(uint32_t w) { return __uint_as_float(w & 0xFFFF0000u); }
__device__ __forceinline__ float bfr(float x) { return __bfloat162float(__float2bfloat16_rn(x)); }
__device__ __forceinline__ uint32_t pack_bf(float lo, float hi) {
    uint32_t r;
    asm("cvt.rn.bf16x2.f32 %0, %1, %2;" : "=r"(r) : "f"(hi), "f"(lo));
    return r;
}
__device__ __forceinline__ float shx(float v, int m) { return __shfl_xor_sync(0xFFFFFFFFu, v, m); }
__device__ __forceinline__ bool warp_any(bool p) { return __any_sync(0xFFFFFFFFu, p); }
__device__ __forceinline__ float ex2(float x) {
    float r;
    asm("ex2.approx.ftz.f32 %0, %1;" : "=f"(r) : "f"(x));
    return r;
}
__device__ __forceinline__ float sqrt_fast(float x) {
    float r;
    asm("sqrt.approx.ftz.f32 %0, %1;" : "=f"(r) : "f"(x));
    return r;
}
constexpr float LOG2E = 1.4426950408889634f;
__device__ __forceinline__ float mul_sigmoid(float v, float z) { return __fdividef(v, 1.f + ex2(-LOG2E * z)); }

__device__ __forceinline__ void block_load(uint32_t (&f)[2][4][4], uint32_t base, int lane) {
    const int mi = lane >> 3, r = lane & 7;
    const uint32_t a = base + ((mi >> 1) * 8 + r) * 128, c0 = (mi & 1) ^ r;
#pragma unroll
    for (int ks = 0; ks < 2; ks++)
#pragma unroll
        for (int mt = 0; mt < 4; mt++) ldsm4t(f[ks][mt], a + ks * 2048 + ((c0 ^ (2 * mt)) << 4));
}
__device__ __forceinline__ void block_mma(float (&acc)[4][4], const uint32_t (&f)[2][4][4], const uint32_t* bf) {
#pragma unroll
    for (int ks = 0; ks < 2; ks++)
#pragma unroll
        for (int mt = 0; mt < 4; mt++) mma(acc[mt], f[ks][mt][0], f[ks][mt][1], f[ks][mt][2], f[ks][mt][3], bf[2 * ks], bf[2 * ks + 1]);
}
__device__ __forceinline__ void block_pick(float (&v)[4], const float (&acc)[4][4], int t) {
#pragma unroll
    for (int i = 0; i < 4; i++) {
        const float lo = (t & 1) ? acc[1][i] : acc[0][i];
        const float hi = (t & 1) ? acc[3][i] : acc[2][i];
        v[i] = (t & 2) ? hi : lo;
    }
}
__device__ __forceinline__ void two_items(float (&v)[4], uint32_t sb, uint32_t bars, int item, const uint32_t (&bf)[8], int w, int lane) {
    float acc[4][4] = {};
#pragma unroll
    for (int h = 0; h < 2; h++) {
        uint32_t f[2][4][4];
        mbar_wait(bars + full_bar(item + h), full_par(item + h));
        block_load(f, sb + slot_addr(item + h) + w * 4096, lane);
        block_mma(acc, f, bf + 4 * h);
    }
    block_pick(v, acc, lane & 3);
}
__device__ __forceinline__ void wait_empty(int src, int lane) {
    const uint32_t* p = g_att + ((lane >> 3) * 64 + src) * 32 + (lane & 7) * 4;
    for (int it = 0;; it++) {
        uint4 v[7];
#pragma unroll
        for (int i = 0; i < 7; i++) v[i] = ld_rlx4(p + i * (4 * 64 * 32));
        uint32_t all = EMPTY;
#pragma unroll
        for (int i = 0; i < 7; i++) all &= v[i].x & v[i].y & v[i].z & v[i].w;
        if (!warp_any(all != EMPTY)) break;
        if (it > SPIN_LIMIT) __trap();
        __nanosleep(300);
    }
}
__device__ __forceinline__ void quad_reduce(float s0, float s1, float s2, float s3, float* red, int w, int lane) {
    const bool u4 = lane & 16, u3 = lane & 8;
    const float a = (u4 ? s2 : s0) + shx(u4 ? s0 : s2, 16);
    const float c = (u4 ? s3 : s1) + shx(u4 ? s1 : s3, 16);
    red[((lane & 7) * 4 + ((lane >> 3) & 2) + ((lane >> 3) & 1)) * 8 + w] = (u3 ? c : a) + shx(u3 ? a : c, 8);
}
__device__ __forceinline__ float sum8(const float* r) {
    const float4 a = *reinterpret_cast<const float4*>(r), b = *reinterpret_cast<const float4*>(r + 4);
    return ((a.x + a.y) + (a.z + a.w)) + ((b.x + b.y) + (b.z + b.w));
}

template <int NHC>
__global__ void __cluster_dims__(8, 1, 1) __launch_bounds__(NTHREADS, 1)
fused_decode_kernel(const __nv_bfloat16* __restrict__ x, const char* __restrict__ kc, __nv_bfloat16* __restrict__ out,
                    const __grid_constant__ CUtensorMap tmWq, const __grid_constant__ CUtensorMap tmWg,
                    const __grid_constant__ CUtensorMap tmWu, const __grid_constant__ CUtensorMap tmV,
                    const __grid_constant__ CUtensorMap tmWo, const __grid_constant__ CUtensorMap tmWd) {
    extern __shared__ char smem_raw[];
    const uint32_t sraw = (uint32_t)__cvta_generic_to_shared(smem_raw);
    const uint32_t sb = (sraw + 1023) & ~1023u;
    char* sm = smem_raw + (sb - sraw);
    const int warp = __shfl_sync(0xFFFFFFFFu, threadIdx.x >> 5, 0), lane = threadIdx.x & 31;
    const int cta = blockIdx.x;
    const uint32_t bars = sb + SM_BAR;
    const bool att = cta < NATT;
    const int rk = cta & 7, hc = (cta - NATT) >> 3;
    const int hx = att ? -1 : NHC == 7 ? (rk < 4 ? hc * 4 + rk : -1) : (cta - NATT < NHELP ? cta - NATT : -1);
    if (!att && hx < 0 && rk == 7) return;

    if (warp >= NMAIN / 32) {
        if (hx >= 0) {
            const int w = warp - NMAIN / 32;
            uint32_t* pa = g_att + hx * 2048 + (threadIdx.x - NMAIN) * 4;
            st_rlx4(pa, EMPTY);
            st_rlx4(pa + 1024, EMPTY);
            const int col = (lane & 1) * D + hx * 16 + (lane & 2) * 4 + (lane >> 2);
            const float xv = __bfloat162float(x[col]);
            float* red3 = reinterpret_cast<float*>(sm + SM_P);
            asm volatile("barrier.cluster.arrive.relaxed.aligned;" ::: "memory");
            if (w == 0) asm volatile("bar.sync 3, 64;" ::: "memory");
            uint4 a = make_uint4(EMPTY, 0, 0, 0), c = a;
            for (int it = 0;; it++) {
                const bool ea = empty4(a), ec = empty4(c);
                if (!warp_any(ea || ec)) break;
                if (it > SPIN_LIMIT) __trap();
                if (!warp_any(!ea || !ec)) __nanosleep(100);
                if (ea) a = ld_rlx4(pa);
                if (ec) c = ld_rlx4(pa + 1024);
            }
            quad_reduce(__uint_as_float(a.x) + __uint_as_float(c.x), __uint_as_float(a.y) + __uint_as_float(c.y),
                        __uint_as_float(a.z) + __uint_as_float(c.z), __uint_as_float(a.w) + __uint_as_float(c.w), red3, w, lane);
            if (w) {
                asm volatile("bar.arrive 4, 256;" ::: "memory");
            } else {
                mbar_wait(bars + B_O * 8, 0);
                const float* di = reinterpret_cast<const float*>(sm + SM_OI) + lane;
                float d0 = ((di[0] + di[32]) + (di[64] + di[96])) + ((di[128] + di[160]) + di[192]);
                if (NHC == 7) d0 += ((di[224] + di[256]) + (di[288] + di[320])) + ((di[352] + di[384]) + di[416]);
                const float dn = bfr(d0);
                const float gate = bfr(mul_sigmoid(dn, dn));
                asm volatile("bar.sync 4, 256;" ::: "memory");
                const float att_sum = bfr(sum8(red3 + lane * 8));
                out[col] = __float2bfloat16_rn(xv + bfr(att_sum * gate));
            }
        } else {
            asm volatile("barrier.cluster.arrive.relaxed.aligned;" ::: "memory");
        }
    } else if (warp == 0) {
        const int row0 = ((cta >> 2) & 1) * (8 * SK) + (cta >> 3) * SK + (SK - WIN) + (cta & 3) * CH;
        const uint32_t t0 = now_ns();
        if (lane == 0) {
            mbar_init(bars + full_bar(0), 1);
            if (att) {
                mbar_expect_tx(bars + full_bar(0), WB);
                tma2d(sb + slot_addr(0), &tmWq, cta * 64, 0, bars + full_bar(0));
            }
            mbar_init(bars + full_bar(1), 1);
            if (att) {
                mbar_expect_tx(bars + full_bar(1), WB);
                tma2d(sb + slot_addr(1), &tmWq, cta * 64, 224, bars + full_bar(1));
            }
            mbar_init(bars + full_bar(2), 1);
            if (att) {
                mbar_expect_tx(bars + full_bar(2), CHB);
                bulk_load(sb + slot_addr(2), kc + (size_t)row0 * 512, CHB, bars + full_bar(2));
            }
#pragma unroll
            for (int i = 3; i < NBAR; i++) mbar_init(bars + i * 8, i < B_EMPTY ? 1 : 8);
            mbar_expect_tx(bars + B_Q * 8, 2048);
            mbar_expect_tx(bars + B_ST * 8, 64);
            mbar_expect_tx(bars + B_O * 8, att ? 2048 : NHC == 7 ? 14 * 128 : 7 * 128);
            asm volatile("fence.mbarrier_init.release.cluster;" ::: "memory");
        }
        __syncwarp();
        asm volatile("bar.arrive 2, %0;" ::"n"(NMAIN) : "memory");
        if (hx >= 0) asm volatile("bar.arrive 3, 64;" ::: "memory");
        asm volatile("barrier.cluster.arrive.relaxed.aligned;" ::: "memory");
        if (att) {
            if (lane == 0) {
                asm volatile("prefetch.tensormap [%0];" ::"l"(&tmV) : "memory");
                asm volatile("prefetch.tensormap [%0];" ::"l"(&tmWo) : "memory");
                int landed = 0, sl = 0, pl = 0;
                int si = 3, pi = 1;
                uint32_t due = t0 + (OFF + PER * 7 / 4 + PER);
#pragma unroll 1
                for (int i = 3; i < NITEM; i++) {
                    for (int it = 0; landed < (i < I_WO ? i - MINF + 1 : i == I_WO ? i : i - NS + 1); it++) {
                        if (i - landed < MAXF && (int)(due - now_ns()) <= 0) break;
                        if (mbar_test(bars + (B_FULL + sl) * 8, pl)) {
                            landed++;
                            if (++sl == NS) { sl = 0; pl ^= 1; }
                        }
                        if (it > 64 * SPIN_LIMIT) __trap();
                    }
                    due += i == I_WO - 1 ? PER + D_WO : PER;
                    if (i >= NS) mbar_wait(bars + (B_EMPTY + si) * 8, pi);
                    const uint32_t fb = bars + (B_FULL + si) * 8, dst = sb + SM_RING + si * CHB;
                    mbar_expect_tx(fb, i < I_WO ? CHB : WB / 2);
                    if (i < I_V) bulk_load(dst, kc + (size_t)(row0 + (i - I_K) * 4 * CH) * 512, CHB, fb);
                    else tma3d(dst, i < I_WO ? &tmV : &tmWo, i < I_WO ? row0 + (i - I_V) * 4 * CH : cta * 64 + (i - I_WO) * 16, fb);
                    if (++si == NS) { si = 0; pi ^= 1; }
                }
            }
        } else if (lane == 0) {
#pragma unroll 1
            for (int i = hx >= 0 ? 0 : 4; i < (rk == 7 ? 4 : NHC == 7 || hc < 3 ? 6 : 5); i++) {
                for (int it = 0; i >= 4 && (int)(t0 + (NHC == 7 ? T_WD7 : T_WD4) - now_ns()) > 0 && it < SPIN_LIMIT; it++) __nanosleep(20);
                const uint32_t fb = bars + (B_FULL + i) * 8, dst = sb + SM_RING + i * CHB;
                mbar_expect_tx(fb, i < 4 ? WB : NHC == 7 ? CHB / 2 : CHB);
                tma2d(dst, i < 2 ? &tmWg : i < 4 ? &tmWu : &tmWd, i < 4 ? hx * 64 : NHC == 7 ? hc * 64 : hc * 128 + (i & 1) * 64,
                      i < 4 ? (i & 1) * 224 : NHC == 7 ? rk * 256 + (i & 1) * 128 : rk * 256, fb);
            }
        }
    } else {
        const int w = warp - 2, tid = threadIdx.x - 64;
        const int g = lane >> 2, t = lane & 3;
        uint32_t* ph = g_h + (cta - NATT) * 256 + tid;
        if (!att && w >= 0) {
            asm volatile("st.relaxed.gpu.global.u32 [%0], %1;" ::"l"(ph), "r"(EMPTY) : "memory");
        }
        if (warp == 1 || warp == 9) {
            const uint32_t* xp = reinterpret_cast<const uint32_t*>(x) + (warp >> 3) * (D / 2) + lane;
            uint32_t u[7];
#pragma unroll
            for (int i = 0; i < 7; i++) u[i] = __ldg(xp + 32 * i);
            float s = 0.f, v = 0.f;
#pragma unroll
            for (int i = 0; i < 7; i++) s += bf_lo(u[i]) + bf_hi(u[i]);
#pragma unroll
            for (int m = 16; m; m >>= 1) s += shx(s, m);
            s *= 1.f / D;
#pragma unroll
            for (int i = 0; i < 7; i++) v = fmaf(bf_lo(u[i]) - s, bf_lo(u[i]) - s, fmaf(bf_hi(u[i]) - s, bf_hi(u[i]) - s, v));
#pragma unroll
            for (int m = 16; m; m >>= 1) v += shx(v, m);
            const float rden = __fdividef(1.f, bfr(sqrt_fast(bfr(bfr(v * (1.f / D)) + 1e-5f))));
            const float mb = bfr(s);
            uint32_t* xo = reinterpret_cast<uint32_t*>(sm + SM_XN) + (warp >> 3) * 240 + lane;
#pragma unroll
            for (int i = 0; i < 7; i++) {
                const uint32_t c = pack_bf(bf_lo(u[i]) - mb, bf_hi(u[i]) - mb);
                xo[32 * i] = pack_bf(bf_lo(c) * rden, bf_hi(c) * rden);
            }
        }
        asm volatile("bar.sync 2, %0;" ::"n"(NMAIN) : "memory");
        asm volatile("barrier.cluster.arrive.relaxed.aligned;" ::: "memory");
        if (warp == 1) {
            if (att) {
                mbar_wait(bars + full_bar(5), 0);
                wait_empty(cta, lane);
            } else if (hx >= 0) {
                const uint32_t* p = g_h + ((lane >> 4) * 8 + (hx >> 2)) * 256 + (hx & 3) * 64 + (lane & 15) * 4;
                for (int it = 0;; it++) {
                    uint32_t all = EMPTY;
#pragma unroll
                    for (int i = 0; i < (NHC + 1) / 2; i++)
                        if (2 * i + (lane >> 4) < NHC) {
                            const uint4 a = ld_rlx4(p + i * 16 * 256);
                            all &= a.x & a.y & a.z & a.w;
                        }
                    if (!warp_any(all != EMPTY)) break;
                    if (it > SPIN_LIMIT) __trap();
                    __nanosleep(300);
                }
            }
            if (lane == 0) mbar_arrive(bars + B_CLR * 8);
        } else {
            float* red = reinterpret_cast<float*>(sm + SM_RED);
            uint32_t xb[8];
            if (w < 7 && (att || hx >= 0)) {
                const uint32_t* xn = reinterpret_cast<const uint32_t*>(sm + SM_XN) + (g & 1) * 240 + w * 16 + t;
#pragma unroll
                for (int i = 0; i < 8; i++) xb[i] = xn[(i >> 2) * 112 + (i & 3) * 4];
                float v[4];
                two_items(v, sb, bars, 0, xb, w, lane);
                float* dst = red + w * 128 + 16 * t + g;
                dst[0] = v[0]; dst[64] = v[1]; dst[8] = v[2]; dst[72] = v[3];
            }
            if (!att) {
                if (hx >= 0) {
                    float* red2 = reinterpret_cast<float*>(sm + SM_SC);
                    if (w < 7) {
                        float v[4];
                        two_items(v, sb, bars, 2, xb, w, lane);
                        float* dst = red2 + w * 128 + 16 * t + g;
                        dst[0] = v[0]; dst[64] = v[1]; dst[8] = v[2]; dst[72] = v[3];
                    }
                    bar_consumers();
                    if (w < 4) {
                        float ga = 0.f, up = 0.f;
#pragma unroll
                        for (int i = 0; i < 7; i++) {
                            ga += red[i * 128 + tid];
                            up += red2[i * 128 + tid];
                        }
                        ga = bfr(ga);
                        const float h = bfr(mul_sigmoid(ga, 2.f * 0.7978845608028654f * (ga + 0.044715f * ga * ga * ga))) * bfr(up);
                        const uint32_t hw = pack_bf(h, shx(h, 1));
                        mbar_wait(bars + B_CLR * 8, 0);
                        const uint32_t hv = __shfl_sync(0xFFFFFFFFu, hw, lane & 30);
                        uint32_t* dst = g_h + ((lane & 1) * 8 + (hx >> 2)) * 256 + (hx & 3) * 64 + (tid >> 1);
#pragma unroll
                        for (int i = 0; i < (NHC + 1) / 2; i++)
                            if (2 * i + (lane & 1) < NHC)
                                asm volatile("st.relaxed.gpu.global.u32 [%0], %1;" ::"l"(dst + i * 16 * 256), "r"(hv) : "memory");
                    }
                }
                asm volatile("barrier.cluster.wait.aligned;" ::: "memory");
                if (rk < 7) {
                    uint32_t* hs = reinterpret_cast<uint32_t*>(sm + SM_QS);
                    uint32_t hv;
                    for (int it = 0;; it++) {
                        asm volatile("ld.relaxed.gpu.global.u32 %0, [%1];" : "=r"(hv) : "l"(ph) : "memory");
                        if (!warp_any(hv == EMPTY)) break;
                        if (it > SPIN_LIMIT) __trap();
                        __nanosleep(300);
                    }
                    const int k2 = (tid >> 6) * 32 + (tid & 31);
                    hs[((tid >> 5) & 1) * 144 + (k2 >> 4) * 16 + (k2 & 3) * 4 + ((k2 >> 2) & 3)] = hv;
                    bar_consumers();
                    if (NHC == 7 || hc < 3 || w < 4) {
                        constexpr int NI = NHC == 7 ? 4 : 8;
                        const int to = NHC == 7 ? w & 3 : w;
                        uint4 hb[NI];
#pragma unroll
                        for (int i = 0; i < NI; i++)
                            hb[i] = *reinterpret_cast<const uint4*>(hs + (g & 1) * 144 + (NHC == 7 ? (i >> 1) * 4 + (w >> 2) * 2 + (i & 1) : i) * 16 + t * 4);
                        const int mi = lane >> 3, r = lane & 7;
                        const uint32_t a = sb + slot_addr(4) + (w >> 2) * (NHC == 7 ? 8192 : CHB) + ((mi >> 1) * 8 + r) * 128 + ((((w & 3) * 2 + (mi & 1)) ^ r) << 4);
                        const uint32_t ra = mapa(sb + SM_OI + (NHC == 7 ? rk * 2 + (w >> 2) : rk) * 128 + g * 16, to), rb = mapa(bars + B_O * 8, to);
                        float c0[4] = {0.f, 0.f, 0.f, 0.f}, c1[4] = {0.f, 0.f, 0.f, 0.f};
#pragma unroll
                        for (int i = 0; i < NI; i++) {
                            if (NHC == 7 ? (i & 1) == 0 : i == 0) mbar_wait(bars + full_bar(4) + (NHC == 7 ? i >> 1 : w >> 2) * 8, 0);
                            const uint32_t ai = a + (NHC == 7 ? (i >> 1) * CHB + (i & 1) * 4096 : i * 4096);
                            uint32_t f0[4], f1[4];
                            ldsm4t(f0, ai);
                            ldsm4t(f1, ai + 2048);
                            mma(c0, f0[0], f0[1], f0[2], f0[3], hb[i].x, hb[i].y);
                            mma(c1, f1[0], f1[1], f1[2], f1[3], hb[i].z, hb[i].w);
                        }
                        if (t == 0) st_async4(ra, c0[0] + c1[0], c0[1] + c1[1], c0[2] + c1[2], c0[3] + c1[3], rb);
                    }
                }
            } else {
                bar_consumers();
                if (lane == 0) {
                    mbar_arrive(bars + B_EMPTY * 8);
                    mbar_arrive(bars + (B_EMPTY + 1) * 8);
                }
                asm volatile("barrier.cluster.wait.aligned;" ::: "memory");
                if (w == 7) {
                    const int c = (rk & 3) * 8 + (lane >> 2);
                    const uint32_t dst = sb + SM_QS + ((lane & 3) * 68 + (c >> 1) * 4 + (rk >> 2)) * 4;
#pragma unroll
                    for (int b = 0; b < 2; b++) {
                        float q0 = 0.f, q1 = 0.f;
#pragma unroll
                        for (int i = 0; i < 7; i++) {
                            const float2 v = *reinterpret_cast<const float2*>(red + i * 128 + b * 64 + lane * 2);
                            q0 += v.x;
                            q1 += v.y;
                        }
                        const uint32_t qw = pack_bf(q0, q1);
#pragma unroll
                        for (int j = 0; j < 4; j++) {
                            const uint32_t ra = mapa(dst, b * 4 + j), rb = mapa(bars + B_Q * 8, b * 4 + j);
                            st_async(ra + (c & 1) * 8, qw, rb);
                            st_async(ra + 272 * 4 + ((c & 1) ^ 1) * 8, qw, rb);
                        }
                    }
                }
                mbar_wait(bars + B_Q * 8, 0);
                const uint32_t* qs = reinterpret_cast<const uint32_t*>(sm + SM_QS);
                float* sc = reinterpret_cast<float*>(sm + SM_SC);
                float* wmax = reinterpret_cast<float*>(sm + SM_WMAX);
                float* wsum = reinterpret_cast<float*>(sm + SM_WSUM);
                int slot = I_K, par = 0;
                {
                    uint4 aq[16];
#pragma unroll
                    for (int k = 0; k < 16; k++) aq[k] = *reinterpret_cast<const uint4*>(qs + (g & 1) * 272 + t * 68 + (k ^ (g >> 1)) * 4);
                    const int r = lane & 7;
                    const uint32_t koff = (8 * w + r) * 512 + (((lane >> 3) ^ r) << 4);
                    const bool diag = t == (g >> 1);
                    float m0 = -INFINITY, m1 = -INFINITY;
#pragma unroll 1
                    for (int i = 0; i < NK; i++) {
                        mbar_wait(bars + (B_FULL + slot) * 8, par);
                        const uint32_t a0 = sb + SM_RING + slot * CHB + koff, a1 = a0 ^ 64;
                        float c0[4] = {0.f, 0.f, 0.f, 0.f}, c1[4] = {0.f, 0.f, 0.f, 0.f};
#pragma unroll
                        for (int it = 0; it < 8; it++) {
                            uint32_t f[4];
                            ldsm4(f, ((it & 1) ? a1 : a0) + (it >> 1) * 128);
                            mma(c0, aq[2 * it].x, aq[2 * it].y, aq[2 * it].z, aq[2 * it].w, f[0], f[1]);
                            mma(c1, aq[2 * it + 1].x, aq[2 * it + 1].y, aq[2 * it + 1].z, aq[2 * it + 1].w, f[2], f[3]);
                        }
                        __syncwarp();
                        if (lane == 0) mbar_arrive(bars + (B_EMPTY + slot) * 8);
                        if (++slot == NS) { slot = 0; par ^= 1; }
                        const float s0 = bfr((g & 1) ? c0[1] + c1[1] : c0[0] + c1[0]);
                        const float s1 = bfr((g & 1) ? c0[3] + c1[3] : c0[2] + c1[2]);
                        if (diag) {
                            sc[i * CH + 8 * w + g] = s0;
                            sc[1024 + i * CH + 8 * w + g] = s1;
                            m0 = fmaxf(m0, s0);
                            m1 = fmaxf(m1, s1);
                        }
                    }
#pragma unroll
                    for (int m = 16; m; m >>= 1) {
                        m0 = fmaxf(m0, shx(m0, m));
                        m1 = fmaxf(m1, shx(m1, m));
                    }
                    if (lane == 0) *reinterpret_cast<float2*>(wmax + 2 * w) = make_float2(m0, m1);
                }
                bar_consumers();
                constexpr float SCALE = 0.0625f * LOG2E;
                uint32_t* pp = reinterpret_cast<uint32_t*>(sm + SM_P);
                float mx0 = wmax[0], mx1 = wmax[1];
#pragma unroll
                for (int i = 1; i < 8; i++) {
                    mx0 = fmaxf(mx0, wmax[2 * i]);
                    mx1 = fmaxf(mx1, wmax[2 * i + 1]);
                }
                {
                    const int h = w >> 2, k8 = (tid & 127) * 8;
                    const float m = h ? mx1 : mx0;
                    const float4 sa = *reinterpret_cast<const float4*>(sc + h * 1024 + k8);
                    const float4 sc2 = *reinterpret_cast<const float4*>(sc + h * 1024 + k8 + 4);
                    const float e0 = ex2((sa.x - m) * SCALE), e1 = ex2((sa.y - m) * SCALE), e2 = ex2((sa.z - m) * SCALE);
                    const float e3 = ex2((sa.w - m) * SCALE), e4 = ex2((sc2.x - m) * SCALE), e5 = ex2((sc2.y - m) * SCALE);
                    const float e6 = ex2((sc2.z - m) * SCALE), e7 = ex2((sc2.w - m) * SCALE);
                    uint32_t* dst = pp + h * 528 + (k8 >> 5) * 16 + ((k8 >> 3) & 3);
                    dst[0] = pack_bf(e0, e1);
                    dst[4] = pack_bf(e2, e3);
                    dst[8] = pack_bf(e4, e5);
                    dst[12] = pack_bf(e6, e7);
                    float l = ((e0 + e1) + (e2 + e3)) + ((e4 + e5) + (e6 + e7));
#pragma unroll
                    for (int mm = 16; mm; mm >>= 1) l += shx(l, mm);
                    if (lane == 0) wsum[w] = l;
                }
                bar_consumers();
                if (tid < 4)
                    st_async4(mapa(sb + SM_ST + (rk & 3) * 16, (rk & 4) + tid), mx0 * SCALE, (wsum[0] + wsum[1]) + (wsum[2] + wsum[3]),
                              mx1 * SCALE, (wsum[4] + wsum[5]) + (wsum[6] + wsum[7]), mapa(bars + B_ST * 8, (rk & 4) + tid));
                {
                    const int mi = lane >> 3, r = lane & 7;
                    const uint32_t voff = (w >> 1) * 8192 + ((mi >> 1) * 8 + r) * 128 + ((((w & 1) * 4 + (mi & 1)) ^ r) << 4);
                    const uint32_t* pq = pp + (g & 1) * 528 + t * 4;
                    float c0[4] = {0.f, 0.f, 0.f, 0.f}, c1[4] = {0.f, 0.f, 0.f, 0.f};
                    float k0 = 0.f, k1 = 0.f;
#pragma unroll 1
                    for (int i = 0; i < NK; i++) {
                        const uint4 p0 = *reinterpret_cast<const uint4*>(pq + i * 32);
                        const uint4 p1 = *reinterpret_cast<const uint4*>(pq + i * 32 + 16);
                        const uint32_t pf8[8] = {p0.x, p0.y, p0.z, p0.w, p1.x, p1.y, p1.z, p1.w};
                        if (i == NK / 2) {
                            mbar_wait(bars + B_ST * 8, 0);
                            const float4* st = reinterpret_cast<const float4*>(sm + SM_ST);
                            const float4 s0 = st[0], s1 = st[1], s2 = st[2], s3 = st[3];
                            const float M0 = fmaxf(fmaxf(s0.x, s1.x), fmaxf(s2.x, s3.x)), M1 = fmaxf(fmaxf(s0.z, s1.z), fmaxf(s2.z, s3.z));
                            const float L0 = (ex2(s0.x - M0) * s0.y + ex2(s1.x - M0) * s1.y) + (ex2(s2.x - M0) * s2.y + ex2(s3.x - M0) * s3.y);
                            const float L1 = (ex2(s0.z - M1) * s0.w + ex2(s1.z - M1) * s1.w) + (ex2(s2.z - M1) * s2.w + ex2(s3.z - M1) * s3.w);
                            k0 = __fdividef(ex2(mx0 * SCALE - M0), L0);
                            k1 = __fdividef(ex2(mx1 * SCALE - M1), L1);
                        }
                        mbar_wait(bars + (B_FULL + slot) * 8, par);
                        const uint32_t a0 = sb + SM_RING + slot * CHB + voff, a1 = a0 ^ 32;
#pragma unroll
                        for (int ks = 0; ks < 4; ks++) {
                            uint32_t f0[4], f1[4];
                            ldsm4t(f0, a0 + ks * 2048);
                            ldsm4t(f1, a1 + ks * 2048);
                            mma(c0, f0[0], f0[1], f0[2], f0[3], pf8[2 * ks], pf8[2 * ks + 1]);
                            mma(c1, f1[0], f1[1], f1[2], f1[3], pf8[2 * ks], pf8[2 * ks + 1]);
                        }
                        __syncwarp();
                        if (lane == 0) mbar_arrive(bars + (B_EMPTY + slot) * 8);
                        if (++slot == NS) { slot = 0; par ^= 1; }
                    }
                    const float h0 = (t & 2) ? ((t & 1) ? c1[2] : c1[0]) : ((t & 1) ? c0[2] : c0[0]);
                    const float h1 = (t & 2) ? ((t & 1) ? c1[3] : c1[1]) : ((t & 1) ? c0[3] : c0[1]);
                    const uint32_t dst = sb + SM_OI + (rk * 84 + (g >> 1) * 20 + ((w & 1) * 4 + t) * 2 + (g & 1)) * 4;
                    st_async(mapa(dst, w >> 1), __float_as_uint(h0 * k0), mapa(bars + B_O * 8, w >> 1));
                    st_async(mapa(dst, 4 + (w >> 1)), __float_as_uint(h1 * k1), mapa(bars + B_O * 8, 4 + (w >> 1)));
                }
                uint32_t* so = reinterpret_cast<uint32_t*>(sm + SM_RED);
                if (w == 7) {
                    const float4* oi = reinterpret_cast<const float4*>(sm + SM_OI) + (lane >> 4) * 84 + ((lane >> 2) & 3) * 5 + (lane & 3);
                    mbar_wait(bars + B_O * 8, 0);
                    const float4 a = oi[0], b = oi[21], c = oi[42], d = oi[63];
                    *reinterpret_cast<uint2*>(so + lane * 2) = make_uint2(pack_bf((a.x + b.x) + (c.x + d.x), (a.y + b.y) + (c.y + d.y)),
                                                                          pack_bf((a.z + b.z) + (c.z + d.z), (a.w + b.w) + (c.w + d.w)));
                    asm volatile("bar.arrive 1, 256;" ::: "memory");
                } else {
                    uint32_t* dst = g_att + ((4 * w + t) * 64 + cta) * 32 + g * 4;
                    asm volatile("" : "+l"(dst));
                    mbar_wait(bars + B_CLR * 8, 0);
                    float acc[4][4] = {}, v[4];
                    bar_consumers();
                    const uint4 oa = *reinterpret_cast<const uint4*>(so + (lane & 7) * 8), oc = *reinterpret_cast<const uint4*>(so + (lane & 7) * 8 + 4);
                    const uint32_t ob[8] = {oa.x, oa.y, oa.z, oa.w, oc.x, oc.y, oc.z, oc.w};
                    const int mi = lane >> 3, r = lane & 7;
                    const uint32_t a = sb + w * 2048 + ((mi >> 1) * 8 + r) * 128, c0 = (mi & 1) ^ r;
#pragma unroll
                    for (int ks = 0; ks < 4; ks++) {
                        uint32_t f[4][4];
                        mbar_wait(bars + full_bar(I_WO + ks), full_par(I_WO + ks));
#pragma unroll
                        for (int mt = 0; mt < 4; mt++) ldsm4t(f[mt], a + slot_addr(I_WO + ks) + ((c0 ^ (2 * mt)) << 4));
#pragma unroll
                        for (int mt = 0; mt < 4; mt++) mma(acc[mt], f[mt][0], f[mt][1], f[mt][2], f[mt][3], ob[2 * ks], ob[2 * ks + 1]);
                    }
                    block_pick(v, acc, t);
                    asm volatile("st.relaxed.gpu.global.v4.f32 [%0], {%1,%2,%3,%4};" ::"l"(dst), "f"(v[0]), "f"(v[1]), "f"(v[2]), "f"(v[3]) : "memory");
                }
            }
        }
    }
    __syncthreads();
}

typedef CUresult (*EncodeTiledFn)(CUtensorMap*, CUtensorMapDataType, cuuint32_t, void*, const cuuint64_t*, const cuuint64_t*,
                                  const cuuint32_t*, const cuuint32_t*, CUtensorMapInterleave, CUtensorMapSwizzle,
                                  CUtensorMapL2promotion, CUtensorMapFloatOOBfill);

void make_map_rows(EncodeTiledFn enc, CUtensorMap* m, const void* base, uint64_t rows, uint32_t cols, uint32_t box_rows) {
    cuuint64_t dims[3] = {64, rows, cols / 64};
    cuuint64_t strides[2] = {(cuuint64_t)cols * 2, 128};
    cuuint32_t box[3] = {64, box_rows, cols / 64};
    cuuint32_t es[3] = {1, 1, 1};
    enc(m, CU_TENSOR_MAP_DATA_TYPE_BFLOAT16, 3, const_cast<void*>(base), dims, strides, box, es, CU_TENSOR_MAP_INTERLEAVE_NONE,
        CU_TENSOR_MAP_SWIZZLE_128B, CU_TENSOR_MAP_L2_PROMOTION_L2_256B, CU_TENSOR_MAP_FLOAT_OOB_FILL_NONE);
}
void make_map_cols(EncodeTiledFn enc, CUtensorMap* m, const void* base, uint32_t rows, uint32_t cols, uint32_t box_rows) {
    cuuint64_t dims[2] = {cols, rows};
    cuuint64_t strides[1] = {(cuuint64_t)cols * 2};
    cuuint32_t box[2] = {64, box_rows};
    cuuint32_t es[2] = {1, 1};
    enc(m, CU_TENSOR_MAP_DATA_TYPE_BFLOAT16, 2, const_cast<void*>(base), dims, strides, box, es, CU_TENSOR_MAP_INTERLEAVE_NONE,
        CU_TENSOR_MAP_SWIZZLE_128B, CU_TENSOR_MAP_L2_PROMOTION_L2_128B, CU_TENSOR_MAP_FLOAT_OOB_FILL_NONE);
}

}

extern "C" void kernel_launch(void* const* d_in, const int* in_sizes, int n_in, void* d_out, int out_size) {
    (void)in_sizes; (void)n_in; (void)out_size;
    static EncodeTiledFn enc = nullptr;
    static int max_clusters = 0;
    if (!enc) {
        void* fn = nullptr;
        cudaDriverEntryPointQueryResult qr;
        cudaGetDriverEntryPoint("cuTensorMapEncodeTiled", &fn, cudaEnableDefault, &qr);
        enc = (EncodeTiledFn)fn;
        cudaFuncSetAttribute(fused_decode_kernel<7>, cudaFuncAttributeMaxDynamicSharedMemorySize, SMEM_BYTES);
        cudaFuncSetAttribute(fused_decode_kernel<4>, cudaFuncAttributeMaxDynamicSharedMemorySize, SMEM_BYTES);
        cudaLaunchConfig_t cfg = {};
        cfg.gridDim = dim3(MAXCTA);
        cfg.blockDim = dim3(NTHREADS);
        cfg.dynamicSmemBytes = SMEM_BYTES;
        cudaOccupancyMaxActiveClusters(&max_clusters, fused_decode_kernel<7>, &cfg);
    }
    CUtensorMap tmWq, tmWg, tmWu, tmV, tmWo, tmWd;
    make_map_cols(enc, &tmWq, d_in[3], D, QD, D / 2);
    make_map_cols(enc, &tmWg, d_in[6], D, FF, D / 2);
    make_map_cols(enc, &tmWu, d_in[7], D, FF, D / 2);
    make_map_rows(enc, &tmV, d_in[2], (uint64_t)16 * SK, 256, CH);
    make_map_rows(enc, &tmWo, d_in[4], QD, D, 16);
        make_map_cols(enc, &tmWd, d_in[8], FF, D, max_clusters >= 15 ? 128 : 256);
    if (max_clusters >= 15)
        fused_decode_kernel<7><<<NATT + 56, NTHREADS, SMEM_BYTES, cudaStreamPerThread>>>(
            (const __nv_bfloat16*)d_in[0], (const char*)d_in[1], (__nv_bfloat16*)d_out, tmWq, tmWg, tmWu, tmV, tmWo, tmWd);
    else
        fused_decode_kernel<4><<<NATT + 32, NTHREADS, SMEM_BYTES, cudaStreamPerThread>>>(
            (const __nv_bfloat16*)d_in[0], (const char*)d_in[1], (__nv_bfloat16*)d_out, tmWq, tmWg, tmWu, tmV, tmWo, tmWd);
}
```
